```python
import torch

def _softmax(x, axis=-1):
    return torch.softmax(x, dim=axis)
def _gelu(x):
    return torch.nn.functional.gelu(x, approximate="tanh")
def _silu(x):
    return torch.nn.functional.silu(x)
def _sigmoid(x):
    return torch.sigmoid(x)
def _layernorm(x, axis=-1, eps=1e-5):
    m = x.mean(dim=axis, keepdim=True)
    v = x.var(dim=axis, keepdim=True, unbiased=False)
    return (x - m) / torch.sqrt(v + eps)
def _scatter_add(tgt, idx, src, axis=0):
    return tgt.clone().index_add_(axis, idx, src)
def _segment_sum(src, seg, n):
    out = torch.zeros((n,) + src.shape[1:], dtype=src.dtype)
    return out.index_add_(0, seg, src)
def _pad(x, pw):
    flat = tuple(v for pair in reversed(pw) for v in pair)
    return torch.nn.functional.pad(x, flat)

kernel_name = 'standalone__glu_gated_swiglu__prompt'

def setup_inputs():

    _w = (lambda a: (lambda t: t.to(torch.bfloat16) if t.is_floating_point() else t)(torch.as_tensor(a)))
    B, S, D, F = 1, 2048, 448, 1792
    return {
        "x": _w((lambda *s: torch.randn(*s, dtype=torch.bfloat16) * 0.05)(B, S, D)),
        "w1": _w((lambda *s: torch.randn(*s, dtype=torch.bfloat16) * 0.05)(D, F) * (2.0 / D) ** 0.5),
        "w3": _w((lambda *s: torch.randn(*s, dtype=torch.bfloat16) * 0.05)(D, F) * (2.0 / D) ** 0.5),
        "w2": _w((lambda *s: torch.randn(*s, dtype=torch.bfloat16) * 0.05)(F, D) * (2.0 / F) ** 0.5),
    }

def reference(x, w1, w3, w2):
    gate = torch.einsum("bsd,df->bsf", x, w1)
    up = torch.einsum("bsd,df->bsf", x, w3)
    h = _silu(gate) * up
    out = torch.einsum("bsf,fd->bsd", h, w2)
    return out
```

```cpp
#include <cuda_runtime.h>
#include <cuda_bf16.h>
#include <cuda.h>
#include <stdint.h>
#include <type_traits>

#define W2COL 224 * odd + 56 * chunk
#define LEAD 2
namespace {

constexpr int kM = 2048, kD = 448, kF = 1792;
constexpr int kNumCtas = 128;

constexpr uint32_t X_OFF = 0;
constexpr uint32_t R_OFF = 114688;
constexpr uint32_t BAR_OFF = 229376;
constexpr uint32_t SMEM_BYTES = BAR_OFF + 1024;

constexpr int B_E1 = 1, B_E3 = 3;
__host__ __device__ constexpr int b_fx(int k) { return k == 0 ? 0 : 4 + k; }
__host__ __device__ constexpr int b_f0(int s) { return 9 + s; }
__host__ __device__ constexpr int b_f1(int t) { return 23 + t; }
__host__ __device__ constexpr int b_f2(int u) { return 30 + u / 6; }
__host__ __device__ constexpr int b_fw(int i) { return 32 + i; }
constexpr int B_TAG = 40;
__host__ __device__ constexpr int b_pace(int i) { return 41 + i; }
__host__ __device__ constexpr int b_c0(int s) { return 45 + s; }
__host__ __device__ constexpr int b_c1(int t) { return 59 + (t < 4 ? t : t - 1); }
__host__ __device__ constexpr int b_c2(int u) { return 65 + u / 3; }
constexpr int B_NUM = 68;
constexpr uint32_t TAG_OFF = BAR_OFF + 768;

__host__ __device__ constexpr uint32_t w2_blk(int i) {
  return i == 0 ? R_OFF : i == 1 ? R_OFF + 28672 : i == 2 ? X_OFF : i == 3 ? X_OFF + 28672
       : i == 4 ? R_OFF + 57344 : i == 5 ? X_OFF + 57344 : i == 6 ? X_OFF + 86016 : R_OFF + 86016;
}
__host__ __device__ constexpr uint32_t g1_off(int t) { return (t < 4 ? t : t - 4) * 16384; }
__host__ __device__ constexpr uint32_t g2_off(int u) { return u < 6 ? 65536 + u * 8192 : 57344; }

__device__ uint4 g_hx[kNumCtas * 14 * 256];
__device__ uint32_t g_epoch[kNumCtas];
#define TS(i)
#define TSG(i)
#define TSR(v)
#define TSW(i, v)
#define TSW2(i, v)
#define TSDUMP()

__device__ __forceinline__ uint32_t smem_u32(const void* p) { return (uint32_t)__cvta_generic_to_shared(p); }
__device__ __forceinline__ void wg_fence() { asm volatile("wgmma.fence.sync.aligned;" ::: "memory"); }
__device__ __forceinline__ void wg_commit() { asm volatile("wgmma.commit_group.sync.aligned;" ::: "memory"); }
template <int N> __device__ __forceinline__ void wg_wait() { asm volatile("wgmma.wait_group.sync.aligned %0;" ::"n"(N) : "memory"); }

__device__ __forceinline__ uint32_t desc_lo(uint32_t addr, uint32_t lbo) { return ((addr & 0x3FFFF) >> 4) | ((lbo >> 4) << 16); }
constexpr int DHI_128 = 0x40000040;
constexpr int DHI_64 = (int)0x80000020u;
template <int I, int N, class Fn> __device__ __forceinline__ void static_for(Fn&& fn) {
  if constexpr (I < N) { fn(std::integral_constant<int, I>{}); static_for<I + 1, N>(fn); }
}

__device__ __forceinline__ void mbar_init(uint32_t a, uint32_t c) { asm volatile("mbarrier.init.shared::cta.b64 [%0], %1;" ::"r"(a), "r"(c) : "memory"); }
__device__ __forceinline__ void mbar_expect(uint32_t a, uint32_t b) { asm volatile("mbarrier.arrive.expect_tx.shared::cta.b64 _, [%0], %1;" ::"r"(a), "r"(b) : "memory"); }
__device__ __forceinline__ void mbar_arrive(uint32_t a) { asm volatile("mbarrier.arrive.shared::cta.b64 _, [%0];" ::"r"(a) : "memory"); }
__device__ __forceinline__ void mbar_arrive_cluster(uint32_t a) { asm volatile("mbarrier.arrive.shared::cluster.b64 _, [%0];" ::"r"(a) : "memory"); }
__device__ __forceinline__ void mbar_wait(uint32_t a) {
  asm volatile("{\n.reg .pred p;\n.reg .u32 n;\n"
               "mbarrier.try_wait.parity.shared::cta.b64 p, [%0], 0;\n@p bra DONE;\nmov.u32 n, 0;\n"
               "LOOP:\nmbarrier.try_wait.parity.shared::cta.b64 p, [%0], 0;\n@p bra DONE;\n"
               "add.u32 n, n, 1;\nsetp.lt.u32 p, n, 0x400000;\n@p bra LOOP;\nexit;\nDONE:\n}" ::"r"(a) : "memory");
}
__device__ __forceinline__ void sched_fence(uint32_t bar) {
  asm volatile("{\n.reg .pred p;\nmbarrier.test_wait.parity.shared::cta.b64 p, [%0], 0;\n}\nwgmma.fence.sync.aligned;" ::"r"(bar) : "memory");
}

__device__ __forceinline__ void tma_load(uint32_t dst, const CUtensorMap* tm, uint32_t bar, int c0, int c1) {
  asm volatile("cp.async.bulk.tensor.2d.shared::cluster.global.mbarrier::complete_tx::bytes [%0], [%1, {%3, %4}], [%2];"
               ::"r"(dst), "l"(tm), "r"(bar), "r"(c0), "r"(c1) : "memory");
}
__device__ __forceinline__ void tma_load_mc(uint32_t dst, const CUtensorMap* tm, uint32_t bar, int c0, int c1) {
  asm volatile("cp.async.bulk.tensor.2d.shared::cluster.global.mbarrier::complete_tx::bytes.multicast::cluster [%0], [%1, {%3, %4}], [%2], %5;"
               ::"r"(dst), "l"(tm), "r"(bar), "r"(c0), "r"(c1), "h"((uint16_t)3) : "memory");
}
__device__ __forceinline__ void tma_prefetch_l2(const CUtensorMap* tm, int c0, int c1) {
  asm volatile("cp.async.bulk.prefetch.tensor.2d.L2.global [%0, {%1, %2}];" ::"l"(tm), "r"(c0), "r"(c1) : "memory");
}
__device__ __forceinline__ void tma_prefetch_desc(const CUtensorMap* tm) { asm volatile("prefetch.tensormap [%0];" ::"l"(tm) : "memory"); }

__device__ __forceinline__ void ld128(uint32_t (&v)[4], const void* p) {
  asm volatile("{\n.reg .b128 t;\n.reg .b64 lo, hi;\nld.relaxed.gpu.global.b128 t, [%4];\nmov.b128 {lo, hi}, t;\nmov.b64 {%0,%1}, lo;\nmov.b64 {%2,%3}, hi;\n}"
               : "=r"(v[0]), "=r"(v[1]), "=r"(v[2]), "=r"(v[3]) : "l"(p) : "memory");
}
__device__ __forceinline__ void st128(void* p, uint32_t a, uint32_t b, uint32_t c, uint32_t d) {
  asm volatile("{\n.reg .b128 t;\n.reg .b64 lo, hi;\nmov.b64 lo, {%1,%2};\nmov.b64 hi, {%3,%4};\nmov.b128 t, {lo, hi};\nst.relaxed.gpu.global.b128 [%0], t;\n}"
               ::"l"(p), "r"(a), "r"(b), "r"(c), "r"(d) : "memory");
}

__device__ __forceinline__ uint32_t pack_bf16(float lo, float hi) {
  uint32_t r;
  asm("cvt.rn.bf16x2.f32 %0, %1, %2;" : "=r"(r) : "f"(hi), "f"(lo));
  return r;
}
__device__ __forceinline__ float silu_mul(float g, float u, float hf) {
  float a = hf * g, t;
  asm("tanh.approx.f32 %0, %1;" : "=f"(t) : "f"(a));
  float p = a * u;
  return fmaf(p, t, p);
}
template <int UO, int R>
__device__ __forceinline__ void silu_step(uint32_t (&h)[4], const float (&d)[R], int j, float hf) {
#pragma unroll
  for (int i = 0; i < 4; i++)
    h[i] = pack_bf16(silu_mul(d[8 * j + 2 * i], d[UO + 8 * j + 2 * i], hf), silu_mul(d[8 * j + 2 * i + 1], d[UO + 8 * j + 2 * i + 1], hf));
}

template <int AOFF, int BOFF, int BHI, int SD>
__device__ __forceinline__ void wgmma_ss_n256(float (&d)[128], uint32_t alo, uint32_t blo) {
  asm volatile("{\n.reg .pred p;\n.reg .b32 al, bl;\n.reg .b64 da, db;\nsetp.ne.b32 p, %133, 0;\n"
    "add.u32 al, %128, %130;\nadd.u32 bl, %129, %131;\nmov.b64 da, {al, 0x40000040};\nmov.b64 db, {bl, %132};\n"
    "wgmma.mma_async.sync.aligned.m64n256k16.f32.bf16.bf16 {%0, %1, %2, %3, %4, %5, %6, %7, %8, %9, %10, %11, %12, %13, %14, %15, %16, %17, %18, %19, %20, %21, %22, %23, %24, %25, %26, %27, %28, %29, %30, %31, %32, %33, %34, %35, %36, %37, %38, %39, %40, %41, %42, %43, %44, %45, %46, %47, %48, %49, %50, %51, %52, %53, %54, %55, %56, %57, %58, %59, %60, %61, %62, %63, %64, %65, %66, %67, %68, %69, %70, %71, %72, %73, %74, %75, %76, %77, %78, %79, %80, %81, %82, %83, %84, %85, %86, %87, %88, %89, %90, %91, %92, %93, %94, %95, %96, %97, %98, %99, %100, %101, %102, %103, %104, %105, %106, %107, %108, %109, %110, %111, %112, %113, %114, %115, %116, %117, %118, %119, %120, %121, %122, %123, %124, %125, %126, %127}, da, db, p, 1, 1, 0, 1;\n}\n"
    : "+f"(d[0]), "+f"(d[1]), "+f"(d[2]), "+f"(d[3]), "+f"(d[4]), "+f"(d[5]), "+f"(d[6]), "+f"(d[7]), "+f"(d[8]), "+f"(d[9]), "+f"(d[10]), "+f"(d[11]), "+f"(d[12]), "+f"(d[13]), "+f"(d[14]), "+f"(d[15]), "+f"(d[16]), "+f"(d[17]), "+f"(d[18]), "+f"(d[19]), "+f"(d[20]), "+f"(d[21]), "+f"(d[22]), "+f"(d[23]), "+f"(d[24]), "+f"(d[25]), "+f"(d[26]), "+f"(d[27]), "+f"(d[28]), "+f"(d[29]), "+f"(d[30]), "+f"(d[31]), "+f"(d[32]), "+f"(d[33]), "+f"(d[34]), "+f"(d[35]), "+f"(d[36]), "+f"(d[37]), "+f"(d[38]), "+f"(d[39]), "+f"(d[40]), "+f"(d[41]), "+f"(d[42]), "+f"(d[43]), "+f"(d[44]), "+f"(d[45]), "+f"(d[46]), "+f"(d[47]), "+f"(d[48]), "+f"(d[49]), "+f"(d[50]), "+f"(d[51]), "+f"(d[52]), "+f"(d[53]), "+f"(d[54]), "+f"(d[55]), "+f"(d[56]), "+f"(d[57]), "+f"(d[58]), "+f"(d[59]), "+f"(d[60]), "+f"(d[61]), "+f"(d[62]), "+f"(d[63]), "+f"(d[64]), "+f"(d[65]), "+f"(d[66]), "+f"(d[67]), "+f"(d[68]), "+f"(d[69]), "+f"(d[70]), "+f"(d[71]), "+f"(d[72]), "+f"(d[73]), "+f"(d[74]), "+f"(d[75]), "+f"(d[76]), "+f"(d[77]), "+f"(d[78]), "+f"(d[79]), "+f"(d[80]), "+f"(d[81]), "+f"(d[82]), "+f"(d[83]), "+f"(d[84]), "+f"(d[85]), "+f"(d[86]), "+f"(d[87]), "+f"(d[88]), "+f"(d[89]), "+f"(d[90]), "+f"(d[91]), "+f"(d[92]), "+f"(d[93]), "+f"(d[94]), "+f"(d[95]), "+f"(d[96]), "+f"(d[97]), "+f"(d[98]), "+f"(d[99]), "+f"(d[100]), "+f"(d[101]), "+f"(d[102]), "+f"(d[103]), "+f"(d[104]), "+f"(d[105]), "+f"(d[106]), "+f"(d[107]), "+f"(d[108]), "+f"(d[109]), "+f"(d[110]), "+f"(d[111]), "+f"(d[112]), "+f"(d[113]), "+f"(d[114]), "+f"(d[115]), "+f"(d[116]), "+f"(d[117]), "+f"(d[118]), "+f"(d[119]), "+f"(d[120]), "+f"(d[121]), "+f"(d[122]), "+f"(d[123]), "+f"(d[124]), "+f"(d[125]), "+f"(d[126]), "+f"(d[127])
    : "r"(alo), "r"(blo), "n"(AOFF), "n"(BOFF), "n"(BHI), "n"(SD));
}
template <int AOFF, int BOFF, int BHI, int SD>
__device__ __forceinline__ void wgmma_ss_n128(float (&d)[64], uint32_t alo, uint32_t blo) {
  asm volatile("{\n.reg .pred p;\n.reg .b32 al, bl;\n.reg .b64 da, db;\nsetp.ne.b32 p, %69, 0;\n"
    "add.u32 al, %64, %66;\nadd.u32 bl, %65, %67;\nmov.b64 da, {al, 0x40000040};\nmov.b64 db, {bl, %68};\n"
    "wgmma.mma_async.sync.aligned.m64n128k16.f32.bf16.bf16 {%0, %1, %2, %3, %4, %5, %6, %7, %8, %9, %10, %11, %12, %13, %14, %15, %16, %17, %18, %19, %20, %21, %22, %23, %24, %25, %26, %27, %28, %29, %30, %31, %32, %33, %34, %35, %36, %37, %38, %39, %40, %41, %42, %43, %44, %45, %46, %47, %48, %49, %50, %51, %52, %53, %54, %55, %56, %57, %58, %59, %60, %61, %62, %63}, da, db, p, 1, 1, 0, 1;\n}\n"
    : "+f"(d[0]), "+f"(d[1]), "+f"(d[2]), "+f"(d[3]), "+f"(d[4]), "+f"(d[5]), "+f"(d[6]), "+f"(d[7]), "+f"(d[8]), "+f"(d[9]), "+f"(d[10]), "+f"(d[11]), "+f"(d[12]), "+f"(d[13]), "+f"(d[14]), "+f"(d[15]), "+f"(d[16]), "+f"(d[17]), "+f"(d[18]), "+f"(d[19]), "+f"(d[20]), "+f"(d[21]), "+f"(d[22]), "+f"(d[23]), "+f"(d[24]), "+f"(d[25]), "+f"(d[26]), "+f"(d[27]), "+f"(d[28]), "+f"(d[29]), "+f"(d[30]), "+f"(d[31]), "+f"(d[32]), "+f"(d[33]), "+f"(d[34]), "+f"(d[35]), "+f"(d[36]), "+f"(d[37]), "+f"(d[38]), "+f"(d[39]), "+f"(d[40]), "+f"(d[41]), "+f"(d[42]), "+f"(d[43]), "+f"(d[44]), "+f"(d[45]), "+f"(d[46]), "+f"(d[47]), "+f"(d[48]), "+f"(d[49]), "+f"(d[50]), "+f"(d[51]), "+f"(d[52]), "+f"(d[53]), "+f"(d[54]), "+f"(d[55]), "+f"(d[56]), "+f"(d[57]), "+f"(d[58]), "+f"(d[59]), "+f"(d[60]), "+f"(d[61]), "+f"(d[62]), "+f"(d[63])
    : "r"(alo), "r"(blo), "n"(AOFF), "n"(BOFF), "n"(BHI), "n"(SD));
}
template <int AOFF, int BOFF, int BHI, int SD>
__device__ __forceinline__ void wgmma_ss_n64(float (&d)[32], uint32_t alo, uint32_t blo) {
  asm volatile("{\n.reg .pred p;\n.reg .b32 al, bl;\n.reg .b64 da, db;\nsetp.ne.b32 p, %37, 0;\n"
    "add.u32 al, %32, %34;\nadd.u32 bl, %33, %35;\nmov.b64 da, {al, 0x40000040};\nmov.b64 db, {bl, %36};\n"
    "wgmma.mma_async.sync.aligned.m64n64k16.f32.bf16.bf16 {%0, %1, %2, %3, %4, %5, %6, %7, %8, %9, %10, %11, %12, %13, %14, %15, %16, %17, %18, %19, %20, %21, %22, %23, %24, %25, %26, %27, %28, %29, %30, %31}, da, db, p, 1, 1, 0, 1;\n}\n"
    : "+f"(d[0]), "+f"(d[1]), "+f"(d[2]), "+f"(d[3]), "+f"(d[4]), "+f"(d[5]), "+f"(d[6]), "+f"(d[7]), "+f"(d[8]), "+f"(d[9]), "+f"(d[10]), "+f"(d[11]), "+f"(d[12]), "+f"(d[13]), "+f"(d[14]), "+f"(d[15]), "+f"(d[16]), "+f"(d[17]), "+f"(d[18]), "+f"(d[19]), "+f"(d[20]), "+f"(d[21]), "+f"(d[22]), "+f"(d[23]), "+f"(d[24]), "+f"(d[25]), "+f"(d[26]), "+f"(d[27]), "+f"(d[28]), "+f"(d[29]), "+f"(d[30]), "+f"(d[31])
    : "r"(alo), "r"(blo), "n"(AOFF), "n"(BOFF), "n"(BHI), "n"(SD));
}
template <int BOFF, int SD>
__device__ __forceinline__ void wgmma_rs_n56(float (&d)[28], const uint32_t (&a)[4], uint32_t blo) {
  asm volatile("{\n.reg .pred p;\n.reg .b32 bl;\n.reg .b64 db;\nsetp.ne.b32 p, %34, 0;\n"
    "add.u32 bl, %32, %33;\nmov.b64 db, {bl, 0x40000040};\n"
    "wgmma.mma_async.sync.aligned.m64n56k16.f32.bf16.bf16 {%0, %1, %2, %3, %4, %5, %6, %7, %8, %9, %10, %11, %12, %13, %14, %15, %16, %17, %18, %19, %20, %21, %22, %23, %24, %25, %26, %27}, {%28, %29, %30, %31}, db, p, 1, 1, 1;\n}\n"
    : "+f"(d[0]), "+f"(d[1]), "+f"(d[2]), "+f"(d[3]), "+f"(d[4]), "+f"(d[5]), "+f"(d[6]), "+f"(d[7]), "+f"(d[8]), "+f"(d[9]), "+f"(d[10]), "+f"(d[11]), "+f"(d[12]), "+f"(d[13]), "+f"(d[14]), "+f"(d[15]), "+f"(d[16]), "+f"(d[17]), "+f"(d[18]), "+f"(d[19]), "+f"(d[20]), "+f"(d[21]), "+f"(d[22]), "+f"(d[23]), "+f"(d[24]), "+f"(d[25]), "+f"(d[26]), "+f"(d[27])
    : "r"(a[0]), "r"(a[1]), "r"(a[2]), "r"(a[3]), "r"(blo), "n"(BOFF), "n"(SD));
}

__device__ __forceinline__ void untag(uint32_t& w) { asm volatile("and.b32 %0, %0, -2;" : "+r"(w)); }

template <bool PAR>
__device__ __forceinline__ void h_send(uint32_t (&h)[4], char* dst, uint32_t par) {
  if (PAR) h[0] = (h[0] & ~1u) | par;
  h[1] |= 1u;
  st128(dst, h[0], h[1], h[2], h[3]);
}
template <int J0, int J1>
__device__ __forceinline__ void h_load(uint32_t (&h)[14][4], const char* src) {
#pragma unroll
  for (int j = J0; j < J1; j++) ld128(h[j], src + j * 4096);
}
template <int J0>
__device__ __forceinline__ void h_check4(uint32_t (&h)[14][4], const char* src, uint32_t zero) {
  asm volatile("{\n.reg .pred p;\n.reg .b32 b, t, n;\n.reg .b128 v;\n.reg .b64 lo, hi;\nmov.u32 n, 0;\n"
               "AGAIN:\nmov.b32 b, %17;\nnot.b32 t, %1;\nor.b32 b, b, t;\nnot.b32 t, %5;\nor.b32 b, b, t;\nnot.b32 t, %9;\nor.b32 b, b, t;\nnot.b32 t, %13;\nor.b32 b, b, t;\nand.b32 b, b, 1;\nsetp.ne.u32 p, b, 0;\nvote.sync.any.pred p, p, 0xffffffff;\n@!p bra OK;\n"
               "add.u32 n, n, 1;\nsetp.gt.u32 p, n, 0x400000;\n@p exit;\n"
               "ld.relaxed.gpu.global.b128 v, [%16 + 0];\nmov.b128 {lo, hi}, v;\nmov.b64 {%0,%1}, lo;\nmov.b64 {%2,%3}, hi;\nld.relaxed.gpu.global.b128 v, [%16 + 4096];\nmov.b128 {lo, hi}, v;\nmov.b64 {%4,%5}, lo;\nmov.b64 {%6,%7}, hi;\nld.relaxed.gpu.global.b128 v, [%16 + 8192];\nmov.b128 {lo, hi}, v;\nmov.b64 {%8,%9}, lo;\nmov.b64 {%10,%11}, hi;\nld.relaxed.gpu.global.b128 v, [%16 + 12288];\nmov.b128 {lo, hi}, v;\nmov.b64 {%12,%13}, lo;\nmov.b64 {%14,%15}, hi;\nbra AGAIN;\nOK:\n}"
               : "+r"(h[J0 + 0][0]), "+r"(h[J0 + 0][1]), "+r"(h[J0 + 0][2]), "+r"(h[J0 + 0][3]), "+r"(h[J0 + 1][0]), "+r"(h[J0 + 1][1]), "+r"(h[J0 + 1][2]), "+r"(h[J0 + 1][3]), "+r"(h[J0 + 2][0]), "+r"(h[J0 + 2][1]), "+r"(h[J0 + 2][2]), "+r"(h[J0 + 2][3]), "+r"(h[J0 + 3][0]), "+r"(h[J0 + 3][1]), "+r"(h[J0 + 3][2]), "+r"(h[J0 + 3][3])
               : "l"(src + J0 * 4096), "r"(zero) : "memory");
}
__device__ __forceinline__ void h_check_last(uint32_t (&h)[14][4], const char* src, uint32_t par, uint32_t zero) {
  asm volatile("{\n.reg .pred p;\n.reg .b32 b, t, n;\n.reg .b128 v;\n.reg .b64 lo, hi;\nmov.u32 n, 0;\n"
               "AGAIN:\nmov.b32 b, %10;\nxor.b32 t, %0, %9;\nor.b32 b, b, t;\nxor.b32 t, %4, %9;\nor.b32 b, b, t;\nand.b32 b, b, 1;\nsetp.ne.u32 p, b, 0;\nvote.sync.any.pred p, p, 0xffffffff;\n@!p bra OK;\n"
               "add.u32 n, n, 1;\nsetp.gt.u32 p, n, 0x400000;\n@p exit;\n"
               "ld.relaxed.gpu.global.b128 v, [%8 + 0];\nmov.b128 {lo, hi}, v;\nmov.b64 {%0,%1}, lo;\nmov.b64 {%2,%3}, hi;\nld.relaxed.gpu.global.b128 v, [%8 + 4096];\nmov.b128 {lo, hi}, v;\nmov.b64 {%4,%5}, lo;\nmov.b64 {%6,%7}, hi;\nbra AGAIN;\nOK:\nand.b32 %0, %0, -2;\nand.b32 %4, %4, -2;\n}"
               : "+r"(h[12 + 0][0]), "+r"(h[12 + 0][1]), "+r"(h[12 + 0][2]), "+r"(h[12 + 0][3]), "+r"(h[12 + 1][0]), "+r"(h[12 + 1][1]), "+r"(h[12 + 1][2]), "+r"(h[12 + 1][3])
               : "l"(src + 12 * 4096), "r"(par), "r"(zero) : "memory");
}
__device__ __forceinline__ void part_check(uint32_t (&p)[4][4], const char* src, uint32_t par, uint32_t zero) {
  asm volatile("{\n.reg .pred p;\n.reg .b32 b, t, n;\n.reg .b128 v;\n.reg .b64 lo, hi;\nmov.u32 n, 0;\n"
               "AGAIN:\nmov.b32 b, %18;\nxor.b32 t, %0, %17;\nor.b32 b, b, t;\nor.b32 b, b, %1;\nxor.b32 t, %4, %17;\nor.b32 b, b, t;\nor.b32 b, b, %5;\nxor.b32 t, %8, %17;\nor.b32 b, b, t;\nor.b32 b, b, %9;\nxor.b32 t, %12, %17;\nor.b32 b, b, t;\nor.b32 b, b, %13;\nand.b32 b, b, 1;\nsetp.ne.u32 p, b, 0;\nvote.sync.any.pred p, p, 0xffffffff;\n@!p bra OK;\n"
               "add.u32 n, n, 1;\nsetp.gt.u32 p, n, 0x400000;\n@p exit;\n"
               "ld.relaxed.gpu.global.b128 v, [%16 + 0];\nmov.b128 {lo, hi}, v;\nmov.b64 {%0,%1}, lo;\nmov.b64 {%2,%3}, hi;\nld.relaxed.gpu.global.b128 v, [%16 + 4096];\nmov.b128 {lo, hi}, v;\nmov.b64 {%4,%5}, lo;\nmov.b64 {%6,%7}, hi;\nld.relaxed.gpu.global.b128 v, [%16 + 8192];\nmov.b128 {lo, hi}, v;\nmov.b64 {%8,%9}, lo;\nmov.b64 {%10,%11}, hi;\nld.relaxed.gpu.global.b128 v, [%16 + 12288];\nmov.b128 {lo, hi}, v;\nmov.b64 {%12,%13}, lo;\nmov.b64 {%14,%15}, hi;\nbra AGAIN;\nOK:\n}"
               : "+r"(p[0][0]), "+r"(p[0][1]), "+r"(p[0][2]), "+r"(p[0][3]), "+r"(p[1][0]), "+r"(p[1][1]), "+r"(p[1][2]), "+r"(p[1][3]), "+r"(p[2][0]), "+r"(p[2][1]), "+r"(p[2][2]), "+r"(p[2][3]), "+r"(p[3][0]), "+r"(p[3][1]), "+r"(p[3][2]), "+r"(p[3][3])
               : "l"(src), "r"(par), "r"(zero) : "memory");
}
template <int V>
__device__ __forceinline__ void part_send(const float (&d)[28], char* dst, uint32_t par) {
  const uint32_t w0 = (pack_bf16(d[8 * V], d[8 * V + 1]) & ~1u) | par, w1 = pack_bf16(d[8 * V + 2], d[8 * V + 3]) & ~1u;
  if constexpr (V < 3) st128(dst + V * 4096, w0, w1, pack_bf16(d[8 * V + 4], d[8 * V + 5]), pack_bf16(d[8 * V + 6], d[8 * V + 7]));
  else st128(dst + V * 4096, w0, w1, 0u, 0u);
}
__device__ __forceinline__ void part_load(uint32_t (&p)[4][4], const char* src) {
#pragma unroll
  for (int v = 0; v < 4; v++) ld128(p[v], src + v * 4096);
}
__device__ __forceinline__ float part_val(const uint32_t (&p)[4][4], int i) {
  const uint32_t w = p[i >> 3][(i >> 1) & 3];
  return __uint_as_float((i & 1) ? (w & 0xffff0000u) : ((i & 7) == 0 ? ((w << 16) & 0xfffe0000u) : (w << 16)));
}

template <int BLK, int J0, int J1, bool ZERO = false>
__device__ __forceinline__ void p2(float (&acc)[28], const uint32_t (&h)[14][4], uint32_t dm, uint32_t dp) {
  wg_fence();
  static_for<J0, J1>([&](auto jc) {
    constexpr int j = decltype(jc)::value;
    wgmma_rs_n56<(int)(w2_blk(BLK) >> 4) + (j < 12 ? j : j - 12) * 128, (ZERO && j == J0) ? 0 : 1>(acc, h[j], j < 12 ? dm : dp);
  });
}

__global__ void __cluster_dims__(2, 1, 1) __launch_bounds__(384, 1)
swiglu_fused_kernel(const __grid_constant__ CUtensorMap tm_x, const __grid_constant__ CUtensorMap tm_w1,
                    const __grid_constant__ CUtensorMap tm_w3, const __grid_constant__ CUtensorMap tm_w1n,
                    const __grid_constant__ CUtensorMap tm_w3n, const __grid_constant__ CUtensorMap tm_w2,
                    const __nv_bfloat16* __restrict__ x, const __nv_bfloat16* __restrict__ w1, const __nv_bfloat16* __restrict__ w3,
                    const __nv_bfloat16* __restrict__ w2, __nv_bfloat16* __restrict__ out) {
  extern __shared__ __align__(1024) uint8_t smem_raw[];
  TSR(t1);
  const uint32_t sb = smem_u32(smem_raw);
  const uint32_t bars = sb + BAR_OFF;
  const int tid = threadIdx.x, lane = tid & 31;
  const int warp = __shfl_sync(0xffffffffu, tid >> 5, 0);
  const int cl = blockIdx.x >> 1;
  const uint32_t rank = blockIdx.x & 1;
  const int f = cl & 7, m = ((cl >> 3) << 1) | (int)rank;
  const int odd = f & 1, q = f >> 1;
  const int a0 = 224 * f + 32 * odd;

  if (warp == 8) {
    if (lane == 0) {
      mbar_init(bars, 1); mbar_expect(bars, 16384);
      tma_load(sb + X_OFF, &tm_x, bars, 0, m * 128);
    }
    __syncwarp();
    asm volatile("bar.arrive 0, 384;" ::: "memory");
  }
  if (warp > 8) {
    const uint32_t b = bars + 8 * (2 * warp - 17);
    const CUtensorMap* tw = warp == 9 ? &tm_w1 : &tm_w3;
    const uint32_t dst = sb + R_OFF + (warp - 9) * 8192;
    if (lane == 0 && warp < 11) {
      mbar_init(b, 1); mbar_init(b + 8, 1); mbar_expect(b, 8192);
      tma_load(dst, tw, b, a0, 0);
      tma_load(dst + 4096, tw, b, a0 + 64, 0);
      TSR(t18); TSW2(18, t18);
      mbar_expect(b + 8, 8192);
    }
    __syncwarp();
    asm volatile("bar.arrive 0, 384;" ::: "memory");
    asm volatile("barrier.cluster.arrive.relaxed.aligned;" ::: "memory");
    if (lane == 0 && warp < 11) {
      tma_load(dst + 16384, tw, b + 8, a0, 32);
      tma_load(dst + 16384 + 4096, tw, b + 8, a0 + 64, 32);
    }
  }
  if (warp == 0) {
    if (lane == 0) static_for<5, 30>([&](auto i) { mbar_init(bars + 8 * decltype(i)::value, 1); });
    __syncwarp();
    if (lane < 25) mbar_expect(bars + 8 * (5 + lane), 16384);
  }
  if (warp == 1) {
    if (lane == 0) static_for<30, 45>([&](auto i) { mbar_init(bars + 8 * decltype(i)::value, 1); });
    __syncwarp();
    if (lane < 10) mbar_expect(bars + 8 * (30 + lane), lane == 0 ? 49152 : lane == 1 ? 8192 : 28672);
  }
  if (warp == 2 && lane == 0) static_for<45, B_NUM>([&](auto i) { mbar_init(bars + 8 * decltype(i)::value, 16); });
  TSR(t17);
  if (warp < 3) {
    asm volatile("fence.mbarrier_init.release.cluster;" ::: "memory");
    asm volatile("bar.arrive 3, 128;" ::: "memory");
  }
  if (warp == 8) asm volatile("bar.sync 3, 128;" ::: "memory");
  if (warp <= 8) asm volatile("barrier.cluster.arrive.relaxed.aligned;" ::: "memory");
  if (warp < 8) asm volatile("bar.sync 0, 384;" ::: "memory");

  if (warp >= 8) {
    asm volatile("setmaxnreg.dec.sync.aligned.u32 40;");
    if (warp == 8) {
      TSR(t19);
      if (lane == 0) tma_load(sb + X_OFF + 16384, &tm_x, bars + 8 * b_fx(1), 64, m * 128);
      __syncwarp();
      asm volatile("barrier.cluster.wait.aligned;" ::: "memory");
      if (lane == 0) {
        TSR(t2);
        const CUtensorMap* tw = rank ? &tm_w3 : &tm_w1;
        const CUtensorMap* twn = rank ? &tm_w3n : &tm_w1n;
        const int pc = 224 * f + (odd ? 0 : 192);
        const uint32_t rdst = sb + R_OFF + rank * 8192;
#pragma unroll
        for (int s = 2; s < 14; s++) {
          if (s >= 7) mbar_wait(bars + 8 * b_c0(s - 7));
          tma_load_mc(rdst + (s % 7) * 16384, tw, bars + 8 * b_f0(s), a0, 32 * s);
          tma_load_mc(rdst + (s % 7) * 16384 + 4096, tw, bars + 8 * b_f0(s), a0 + 64, 32 * s);
          if ((s & 1) && s < 13) tma_load(sb + X_OFF + (s / 2 + 1) * 16384, &tm_x, bars + 8 * b_fx(s / 2 + 1), 64 * (s / 2 + 1), m * 128);
          if (s == 6) { tma_prefetch_desc(twn); tma_prefetch_desc(&tm_w2); }
          if (s == 12) asm volatile("cp.async.bulk.prefetch.L2.global [%0], %1;" ::"l"((const char*)w2 + blockIdx.x * 12544), "r"(12544) : "memory");
        }
        auto load_g1 = [&](int t) {
          tma_load_mc(rdst + g1_off(t), tw, bars + 8 * b_f1(t), a0 + 128, 64 * t);
          tma_load_mc(rdst + g1_off(t) + 4096, tw, bars + 8 * b_f1(t), a0 + 128, 64 * t + 32);
        };
        auto load_g2 = [&](int u) { tma_load_mc(sb + R_OFF + g2_off(u) + rank * 4096, twn, bars + 8 * b_f2(u), pc, 64 * u); };
#pragma unroll
        for (int t = 0; t < 4; t++) { mbar_wait(bars + 8 * b_c0(7 + t)); load_g1(t); }
#pragma unroll
        for (int t = 4; t < 7; t++) {
          mbar_wait(bars + 8 * b_c0(7 + t)); load_g2(2 * t - 8); load_g2(2 * t - 7);
          tma_prefetch_l2(tw, a0 + 128, 64 * t); tma_prefetch_l2(tw, a0 + 128, 64 * t + 32);
        }
        tma_prefetch_l2(twn, pc, 64 * 6);
#pragma unroll
        for (int t = 4; t < 7; t++) { mbar_wait(bars + 8 * b_c1(t - 4)); load_g1(t); }
        mbar_wait(bars + 8 * b_c1(3)); load_g2(6);
        const int row_own = 224 * f + 112 * rank, row_peer = 224 * (f ^ 1) + 112 * rank;
#pragma unroll
        for (int i = 0; i < 8; i++) {
          if (i == 0) mbar_wait(bars + 8 * b_c1(5));
          if (i == 1) mbar_wait(bars + 8 * b_c1(6));
          if (i == 2) mbar_wait(bars + 8 * b_c2(1));
          if (i == 3) mbar_wait(bars + 8 * b_c2(3));
          if (i == 4) mbar_wait(bars + 8 * b_c2(6));
          if (i >= 5) mbar_wait(bars + 8 * b_pace(i - 5));
          const int chunk = (q + 1 + (i >> 1)) & 3;
          tma_load_mc(sb + w2_blk(i) + rank * 14336, &tm_w2, bars + 8 * b_fw(i), W2COL, (i & 1) ? row_peer : row_own);
        }
        TS(3); TSW(2, t2); TSW(17, t17); TSW(19, t19);
      }
      TSDUMP();
    } else {
      if (warp == 11 && lane == 0) {
        const uint32_t e = g_epoch[blockIdx.x] + 1;
        g_epoch[blockIdx.x] = e;
        asm volatile("st.shared.u32 [%0], %1;" ::"r"(sb + TAG_OFF), "r"(e & 1u) : "memory");
      }
      __syncwarp();
      asm volatile("barrier.cluster.wait.aligned;" ::: "memory");
      if (warp == 11 && lane == 0) mbar_arrive(bars + 8 * B_TAG);
    }
  } else {
    TSR(t19);
    const int g = warp >> 2;
    uint32_t cbars;
    asm volatile("mapa.shared::cluster.u32 %0, %1, %2;" : "=r"(cbars) : "r"(bars), "r"(lane & 1));
#define SF() sched_fence(bars + 8 * B_TAG)
#define SFI(i) SF()
    auto zero_now = [&]() { uint32_t lo, hi; asm volatile("{\n.reg .b64 t;\nmov.u64 t, %%clock64;\nmov.b64 {%0, %1}, t;\n}" : "=r"(lo), "=r"(hi) :: "memory"); return hi >> 31; };
    auto half = [&]() { return __uint_as_float(0x3f000000u | zero_now()); };
    auto pace = [&](int i) { if (tid == 0) mbar_arrive(bars + 8 * b_pace(i)); };
    auto release = [&](int b) { if (lane < 2) mbar_arrive_cluster(cbars + 8 * b); };

    const uint32_t dx = desc_lo(sb + X_OFF + g * 8192, 16);
    const uint32_t db0 = desc_lo(sb + R_OFF, 4096);
    const uint32_t db1 = desc_lo(sb + R_OFF, 8192);

    uint32_t ho[14][4], hp[14][4];
    char* hx_own = (char*)g_hx + (size_t)blockIdx.x * 57344 + tid * 16;
    char* hx_peer = (char*)g_hx + (size_t)(blockIdx.x ^ 2) * 57344 + tid * 16;
    uint32_t par;
    float accC[32];
    {
      float accB[64];
      {
        float accA[128];
        static_for<0, 14>([&](auto sc) {
          constexpr int s = decltype(sc)::value;
          if ((s & 1) == 0) mbar_wait(bars + 8 * b_fx(s / 2));
          if (s < 2) { mbar_wait(bars + 8 * (B_E1 + s)); mbar_wait(bars + 8 * (B_E3 + s)); } else mbar_wait(bars + 8 * b_f0(s));
          wg_fence();
          wgmma_ss_n256<(s / 2) * 1024 + (s & 1) * 4, (s % 7) * 1024, DHI_128, s ? 1 : 0>(accA, dx, db0);
          wgmma_ss_n256<(s / 2) * 1024 + (s & 1) * 4 + 2, (s % 7) * 1024 + 128, DHI_128, 1>(accA, dx, db0);
          wg_commit();
          if (s == 1) asm volatile("barrier.cluster.wait.aligned;" ::: "memory");
          if (s == 12) asm volatile("setmaxnreg.inc.sync.aligned.u32 232;");
          if (s > 0) { wg_wait<1>(); release(b_c0(s - 1)); }
        });
        TS(3);
        mbar_wait(bars + 8 * B_TAG);
        asm volatile("ld.shared.u32 %0, [%1];" : "=r"(par) : "r"(sb + TAG_OFF) : "memory");
        static_for<0, 7>([&](auto tc) {
          constexpr int t = decltype(tc)::value;
          TS(80 + 2 * t);
          mbar_wait(bars + 8 * b_f1(t));
          TS(81 + 2 * t);
          wg_fence();
          constexpr int bo = g1_off(t) >> 4;
          wgmma_ss_n128<t * 1024, bo, DHI_128, t ? 1 : 0>(accB, dx, db1);
          wgmma_ss_n128<t * 1024 + 2, bo + 128, DHI_128, 1>(accB, dx, db1);
          wgmma_ss_n128<t * 1024 + 4, bo + 256, DHI_128, 1>(accB, dx, db1);
          wgmma_ss_n128<t * 1024 + 6, bo + 384, DHI_128, 1>(accB, dx, db1);
          wg_commit();
          if constexpr (t == 0) { wg_wait<1>(); release(b_c0(13)); }
          SFI(t);
          if constexpr (t >= 4) h_load<t - 4, t - 3>(hp, hx_peer);
          silu_step<64>(ho[t], accA, t, half()); h_send<false>(ho[t], hx_own + t * 4096, par);
          if constexpr (t == 3) { silu_step<64>(ho[7], accA, 7, half()); h_send<false>(ho[7], hx_own + 7 * 4096, par); }
          if constexpr (t > 0) { SFI(t); wg_wait<1>(); if (t != 5) release(b_c1(t - 1)); }
        });
      }
      TS(4);
      auto e1_step = [&](auto jc) {
        constexpr int j = decltype(jc)::value;
        silu_step<32>(ho[8 + j], accB, j, half());
        h_send<false>(ho[8 + j], hx_own + (8 + j) * 4096, par);
      };
      if (g == 1) {
        wg_wait<0>(); release(b_c1(6));
        SF();
        static_for<0, LEAD>(e1_step);
        SF();
      }
      static_for<0, 7>([&](auto uc) {
        constexpr int u = decltype(uc)::value;
        if (u == 0 || u == 6) mbar_wait(bars + 8 * b_f2(u));
        TS(53 + u);
        wg_fence();
        constexpr int bo = g2_off(u) >> 4;
        wgmma_ss_n64<u * 1024, bo, DHI_64, u ? 1 : 0>(accC, dx, db0);
        wgmma_ss_n64<u * 1024 + 2, bo + 64, DHI_64, 1>(accC, dx, db0);
        wgmma_ss_n64<u * 1024 + 4, bo + 128, DHI_64, 1>(accC, dx, db0);
        wgmma_ss_n64<u * 1024 + 6, bo + 192, DHI_64, 1>(accC, dx, db0);
        wg_commit();
        if constexpr (u == 1) { if (g == 0) { wg_wait<2>(); release(b_c1(6)); } }
        SF();
        if constexpr (u == 0) { h_load<3, 5>(hp, hx_peer); h_load<7, 8>(hp, hx_peer); }
        if constexpr (u == 3) h_load<5, 7>(hp, hx_peer);
        if constexpr (u == 1 || u == 2 || u == 4 || u == 5) {
          constexpr int j = u < 3 ? u - 1 : u - 2;
          if (j >= LEAD || g == 0) e1_step(std::integral_constant<int, j>{});
        }
        if constexpr (u == 3 || u == 5) { SF(); wg_wait<2>(); release(b_c2(u - 2)); }
        if constexpr (u != 3 && u != 5 && u != 6) SF();
      });
    }
    TS(5);

    const uint32_t om = odd ? 4096u : 0u, op = odd ? 0u : 24576u;
    const uint32_t d_om = desc_lo(sb + om, 16), d_op = desc_lo(sb + op, 16);
    const uint32_t d_pm = desc_lo(sb + 4096u - om, 16), d_pp = desc_lo(sb + 24576u - op, 16);
#define OWN ho, d_om, d_op
#define PEER hp, d_pm, d_pp
    auto p_src = [&](int i) { return (const char*)g_hx + (size_t)(((blockIdx.x & ~12u) | (((q + 3 - i) & 3) << 2)) ^ 2) * 57344 + i * 16384 + tid * 16; };
    float accP[28], accQ[28];
    uint32_t pa[4][4], pb[4][4], pc[4][4];

    mbar_wait(bars + 8 * b_fw(0));
    TS(21);
    p2<0, 0, 6, true>(accP, OWN);
    wg_commit();
    SF();
    h_check4<0>(hp, hx_peer, zero_now()); h_check4<4>(hp, hx_peer, zero_now());
    h_load<8, 10>(hp, hx_peer);
    SF();
    wg_wait<1>();
    TS(22);
    release(b_c2(6));
    p2<0, 6, 8>(accP, OWN);
    SF();
    silu_step<16>(ho[12], accC, 0, half()); h_send<true>(ho[12], hx_own + 12 * 4096, par);
    SF();
    p2<0, 8, 12>(accP, OWN);
    SF();
    h_load<10, 12>(hp, hx_peer);
    SF();
    silu_step<16>(ho[13], accC, 1, half()); h_send<true>(ho[13], hx_own + 13 * 4096, par);
    TS(23);
    mbar_wait(bars + 8 * b_fw(1));
    TS(25);
    pace(0);
    p2<1, 0, 8>(accP, PEER);
    untag(ho[12][0]); untag(ho[13][0]);
    p2<0, 12, 14>(accP, OWN);
    mbar_wait(bars + 8 * b_fw(2));
    p2<2, 0, 6, true>(accQ, OWN);
    SF();
    TS(27);
    h_check4<8>(hp, hx_peer, zero_now());
    TS(28);
    pace(1);
    p2<1, 8, 12>(accP, PEER);
    SF();
    h_load<12, 14>(hp, hx_peer);
    SF();
    p2<2, 6, 14>(accQ, OWN);
    mbar_wait(bars + 8 * b_fw(3));
    pace(2);
    p2<3, 0, 2>(accQ, PEER);
    SF();
    TS(36);
    h_check_last(hp, hx_peer, par, zero_now());
    TS(37);
    p2<1, 12, 14>(accP, PEER);
    wg_commit();
    p2<3, 2, 8>(accQ, PEER);
    wg_commit();
    wg_wait<1>();
    TS(8);
    asm volatile("bar.arrive %0, 256;" ::"r"(1 + g) : "memory");
    SF();
    part_send<0>(accP, hx_peer, par);
    part_send<1>(accP, hx_peer, par);
    SF();
    p2<3, 8, 11>(accQ, PEER);
    SF();
    part_send<2>(accP, hx_peer, par);
    part_send<3>(accP, hx_peer, par);
    SF();
    p2<3, 11, 14>(accQ, PEER);
    wg_commit();
    mbar_wait(bars + 8 * b_fw(4));
    p2<4, 0, 6, true>(accP, OWN);
    wg_commit();
    wg_wait<1>();
    TS(9);
    SF();
    part_send<0>(accQ, hx_peer + 16384, par);
    part_send<1>(accQ, hx_peer + 16384, par);
    SF();
    p2<4, 6, 10>(accP, OWN);
    SF();
    part_send<2>(accQ, hx_peer + 16384, par);
    part_send<3>(accQ, hx_peer + 16384, par);
    SF();
    p2<4, 10, 14>(accP, OWN);
    mbar_wait(bars + 8 * b_fw(5));
    p2<5, 0, 14>(accP, PEER);
    wg_commit();
    TS(10);
    SF();
    part_load(pa, p_src(0));
    mbar_wait(bars + 8 * b_fw(6));
    p2<6, 0, 6, true>(accQ, OWN);
    wg_commit();
    SF();
    part_load(pb, p_src(1));
    SF();
    TS(40);
    wg_wait<1>();
    TS(11);
    part_send<0>(accP, hx_peer + 32768, par);
    part_send<1>(accP, hx_peer + 32768, par);
    part_send<2>(accP, hx_peer + 32768, par);
    part_send<3>(accP, hx_peer + 32768, par);
    SF();
    TS(41);
    p2<6, 6, 14>(accQ, OWN);
    mbar_wait(bars + 8 * b_fw(7));
    p2<7, 0, 6>(accQ, PEER);
    SF();
    TS(48);
    part_check(pa, p_src(0), par, zero_now());
    part_check(pb, p_src(1), par, zero_now());
    TS(49);
    part_load(pc, p_src(2));
    SF();
    p2<7, 6, 10>(accQ, PEER);
    SF();
#pragma unroll
    for (int i = 0; i < 28; i++) accP[i] = part_val(pa, i) + part_val(pb, i);
    p2<7, 10, 14>(accQ, PEER);
    wg_commit();
    asm volatile("bar.sync %0, 256;" ::"r"(2 - g) : "memory");
    SF();
    TS(12);
    part_check(pc, p_src(2), par, zero_now());
    TS(13);
#pragma unroll
    for (int i = 0; i < 28; i++) accP[i] += part_val(pc, i);
    wg_wait<0>();
    TS(14);
    {
      uint32_t o[14];
#pragma unroll
      for (int i = 0; i < 14; i++) o[i] = pack_bf16(accQ[2 * i] + accP[2 * i], accQ[2 * i + 1] + accP[2 * i + 1]);
      const uint32_t tile = sb + w2_blk(0) + warp * 1792;
      const uint32_t sa = tile + ((lane & 7) + ((lane >> 3) & 1) * 8) * 112 + (lane >> 4) * 16;
#pragma unroll
      for (int k = 0; k < 3; k++)
        asm volatile("stmatrix.sync.aligned.m8n8.x4.shared.b16 [%0], {%1, %2, %3, %4};" ::"r"(sa + k * 32), "r"(o[4 * k]), "r"(o[4 * k + 1]), "r"(o[4 * k + 2]), "r"(o[4 * k + 3]) : "memory");
      asm volatile("stmatrix.sync.aligned.m8n8.x2.shared.b16 [%0], {%1, %2};" ::"r"(tile + (lane & 15) * 112 + 96), "r"(o[12]), "r"(o[13]) : "memory");
      __syncwarp();
      TS(26);
      char* obase = (char*)(out + (size_t)(m * 128 + warp * 16) * kD + 224 * odd + 56 * q);
#pragma unroll
      for (int k = 0; k < 4; k++) {
        const int c = k * 32 + lane;
        if (k < 3 || lane < 16) {
          uint4 v;
          asm volatile("ld.shared.v4.b32 {%0, %1, %2, %3}, [%4];" : "=r"(v.x), "=r"(v.y), "=r"(v.z), "=r"(v.w) : "r"(tile + c * 16) : "memory");
          const int r = (c * 9363) >> 16;
          asm volatile("st.global.v4.b32 [%0], {%1, %2, %3, %4};" ::"l"(obase + r * (kD * 2) + (c - r * 7) * 16), "r"(v.x), "r"(v.y), "r"(v.z), "r"(v.w) : "memory");
        }
      }
    }
    TS(15); TSG(31); TSDUMP();
  }
}

typedef CUresult (*EncodeFn)(CUtensorMap*, CUtensorMapDataType, cuuint32_t, void*, const cuuint64_t*, const cuuint64_t*,
                             const cuuint32_t*, const cuuint32_t*, CUtensorMapInterleave, CUtensorMapSwizzle,
                             CUtensorMapL2promotion, CUtensorMapFloatOOBfill);

void make_map(EncodeFn fn, CUtensorMap* tm, const void* p, uint64_t cols, uint64_t rows, uint32_t bc, uint32_t br, CUtensorMapSwizzle sw) {
  cuuint64_t dims[2] = {cols, rows};
  cuuint64_t strides[1] = {cols * 2};
  cuuint32_t box[2] = {bc, br};
  cuuint32_t es[2] = {1, 1};
  fn(tm, CU_TENSOR_MAP_DATA_TYPE_BFLOAT16, 2, const_cast<void*>(p), dims, strides, box, es, CU_TENSOR_MAP_INTERLEAVE_NONE, sw,
     CU_TENSOR_MAP_L2_PROMOTION_L2_128B, CU_TENSOR_MAP_FLOAT_OOB_FILL_NONE);
}

}

extern "C" void kernel_launch(void* const* d_in, const int* in_sizes, int n_in, void* d_out, int out_size) {
  (void)in_sizes; (void)n_in; (void)out_size;
  static EncodeFn fn = nullptr;
  if (!fn) {
    void* p = nullptr;
    cudaDriverEntryPointQueryResult qr;
    cudaGetDriverEntryPoint("cuTensorMapEncodeTiled", &p, cudaEnableDefault, &qr);
    fn = (EncodeFn)p;
    cudaFuncSetAttribute(swiglu_fused_kernel, cudaFuncAttributeMaxDynamicSharedMemorySize, SMEM_BYTES);
  }
  CUtensorMap tx, tw1, tw3, tw1n, tw3n, tw2;
  make_map(fn, &tx, d_in[0], kD, kM, 64, 128, CU_TENSOR_MAP_SWIZZLE_128B);
  make_map(fn, &tw1, d_in[1], kF, kD, 64, 32, CU_TENSOR_MAP_SWIZZLE_128B);
  make_map(fn, &tw3, d_in[2], kF, kD, 64, 32, CU_TENSOR_MAP_SWIZZLE_128B);
  make_map(fn, &tw1n, d_in[1], kF, kD, 32, 64, CU_TENSOR_MAP_SWIZZLE_64B);
  make_map(fn, &tw3n, d_in[2], kF, kD, 32, 64, CU_TENSOR_MAP_SWIZZLE_64B);
  make_map(fn, &tw2, d_in[3], kD, kF, 64, 112, CU_TENSOR_MAP_SWIZZLE_128B);
  swiglu_fused_kernel<<<kNumCtas, 384, SMEM_BYTES>>>(tx, tw1, tw3, tw1n, tw3n, tw2, (const __nv_bfloat16*)d_in[0],
      (const __nv_bfloat16*)d_in[1], (const __nv_bfloat16*)d_in[2], (const __nv_bfloat16*)d_in[3], (__nv_bfloat16*)d_out);
}
```

```cpp
#include <cuda_runtime.h>
#include <cuda_bf16.h>
#include <cuda.h>
#include <stdint.h>
#include <type_traits>

namespace {

constexpr int kM = 2048, kD = 448, kF = 1792;
constexpr int kNumCtas = 128;

constexpr uint32_t X_OFF = 0;
constexpr uint32_t R_OFF = 114688;
constexpr uint32_t BAR_OFF = 229376;
constexpr uint32_t TAG_OFF = BAR_OFF + 768;
constexpr uint32_t SMEM_BYTES = BAR_OFF + 1024;

__host__ __device__ constexpr int b_fx(int k) { return k < 5 ? 2 + k : 8 + k; }
__host__ __device__ constexpr int b_fu(int n) { return n < 7 ? 6 + n : 8 + n; }
__host__ __device__ constexpr int b_fs(int u) { return 30 + u / 4; }
__host__ __device__ constexpr int b_fw(int i) { return 32 + i; }
constexpr int B_TAG = 40, B_PACE = 41;
__host__ __device__ constexpr int b_cu(int n) { return 45 + n - (n > 18); }
__host__ __device__ constexpr int b_cs(int u) { return 65 + u / 3; }
__host__ __device__ constexpr int b_st(int i) { return 68 + i; }
__host__ __device__ constexpr int b_wg(int k) { return 78 + 2 * k; }
constexpr int B_NUM = 84;

__host__ __device__ constexpr int u_grp(int n) { return n < 6 ? n & 1 : n < 10 ? 0 : n < 14 ? 1 : 2; }
__host__ __device__ constexpr int u_kb(int n) { return n < 6 ? n / 2 : n < 10 ? n - 3 : n < 14 ? n - 7 : n - 14; }
__host__ __device__ constexpr bool u_newx(int n) { return u_grp(n) == 0; }

__host__ __device__ constexpr uint32_t w2_blk(int i) {
  return i == 0 ? R_OFF + 57344 : i == 1 ? R_OFF + 86016 : i == 2 ? X_OFF : i == 3 ? X_OFF + 28672
       : i == 4 ? R_OFF : i == 5 ? X_OFF + 57344 : i == 6 ? X_OFF + 86016 : R_OFF + 28672;
}
__host__ __device__ constexpr uint32_t stg_off(int i) {
  return i == 0 ? w2_blk(7) : i == 1 ? w2_blk(0) : i == 2 ? w2_blk(1) : (i == 3 ? w2_blk(7) : w2_blk(0)) + 16384;
}

__device__ uint4 g_hx[kNumCtas * 14 * 256];
__device__ uint32_t g_epoch[kNumCtas];
__device__ uint32_t g_zflag[kNumCtas];

__device__ __forceinline__ uint32_t smem_u32(const void* p) { return (uint32_t)__cvta_generic_to_shared(p); }
__device__ __forceinline__ void wg_fence() { asm volatile("wgmma.fence.sync.aligned;" ::: "memory"); }
__device__ __forceinline__ void wg_commit() { asm volatile("wgmma.commit_group.sync.aligned;" ::: "memory"); }
template <int N> __device__ __forceinline__ void wg_wait() { asm volatile("wgmma.wait_group.sync.aligned %0;" ::"n"(N) : "memory"); }
template <int R> __device__ __forceinline__ void acc_ready(float (&d)[R]) {
#pragma unroll
  for (int i = 0; i < R; i++) asm volatile("" : "+f"(d[i])::"memory");
}

__device__ __forceinline__ uint32_t desc_lo(uint32_t addr, uint32_t lbo) { return ((addr & 0x3FFFF) >> 4) | ((lbo >> 4) << 16); }
constexpr int DHI_128 = 0x40000040;
constexpr int DHI_64 = (int)0x80000020u;
template <int I, int N, class Fn> __device__ __forceinline__ void static_for(Fn&& fn) {
  if constexpr (I < N) { fn(std::integral_constant<int, I>{}); static_for<I + 1, N>(fn); }
}

__device__ __forceinline__ void mbar_init(uint32_t a, uint32_t c) { asm volatile("mbarrier.init.shared::cta.b64 [%0], %1;" ::"r"(a), "r"(c) : "memory"); }
__device__ __forceinline__ void mbar_expect(uint32_t a, uint32_t b) { asm volatile("mbarrier.arrive.expect_tx.shared::cta.b64 _, [%0], %1;" ::"r"(a), "r"(b) : "memory"); }
__device__ __forceinline__ void mbar_arrive(uint32_t a) { asm volatile("mbarrier.arrive.shared::cta.b64 _, [%0];" ::"r"(a) : "memory"); }
__device__ __forceinline__ void mbar_arrive_cluster(uint32_t a) { asm volatile("mbarrier.arrive.shared::cluster.b64 _, [%0];" ::"r"(a) : "memory"); }
__device__ __forceinline__ void mbar_wait(uint32_t a) {
  asm volatile("{\n.reg .pred p;\n.reg .u32 n;\n"
               "mbarrier.try_wait.parity.shared::cta.b64 p, [%0], 0;\n@p bra DONE;\nmov.u32 n, 0;\n"
               "LOOP:\nmbarrier.try_wait.parity.shared::cta.b64 p, [%0], 0;\n@p bra DONE;\n"
               "add.u32 n, n, 1;\nsetp.lt.u32 p, n, 0x40000;\n@p bra LOOP;\nexit;\nDONE:\n}" ::"r"(a) : "memory");
}
__device__ __forceinline__ void sched_fence(uint32_t bar) {
  asm volatile("{\n.reg .pred p;\nmbarrier.test_wait.parity.shared::cta.b64 p, [%0], 0;\n}\nwgmma.fence.sync.aligned;" ::"r"(bar) : "memory");
}
__device__ __forceinline__ uint32_t zero_now() {
  uint32_t hi;
  asm volatile("{\n.reg .b64 t;\n.reg .b32 lo;\nmov.u64 t, %%clock64;\nmov.b64 {lo, %0}, t;\n}" : "=r"(hi)::"memory");
  return hi >> 31;
}
__device__ __forceinline__ float half_now() { return __uint_as_float(0x3f000000u | zero_now()); }
__device__ __forceinline__ void cluster_arrive() { asm volatile("barrier.cluster.arrive.relaxed.aligned;" ::: "memory"); }
__device__ __forceinline__ void cluster_wait() { asm volatile("barrier.cluster.wait.aligned;" ::: "memory"); }

__device__ __forceinline__ void tma_load(uint32_t dst, const CUtensorMap* tm, uint32_t bar, int c0, int c1) {
  asm volatile("cp.async.bulk.tensor.2d.shared::cluster.global.mbarrier::complete_tx::bytes [%0], [%1, {%3, %4}], [%2];"
               ::"r"(dst), "l"(tm), "r"(bar), "r"(c0), "r"(c1) : "memory");
}
__device__ __forceinline__ void tma_load_mc(uint32_t dst, const CUtensorMap* tm, uint32_t bar, int c0, int c1) {
  asm volatile("cp.async.bulk.tensor.2d.shared::cluster.global.mbarrier::complete_tx::bytes.multicast::cluster [%0], [%1, {%3, %4}], [%2], %5;"
               ::"r"(dst), "l"(tm), "r"(bar), "r"(c0), "r"(c1), "h"((uint16_t)3) : "memory");
}
__device__ __forceinline__ void tma_prefetch_desc(const CUtensorMap* tm) { asm volatile("prefetch.tensormap [%0];" ::"l"(tm) : "memory"); }
__device__ __forceinline__ void cp_async16(uint32_t dst, const void* src) {
  asm volatile("cp.async.cg.shared.global [%0], [%1], 16;" ::"r"(dst), "l"(src) : "memory");
}

__device__ __forceinline__ uint32_t pack_bf16(float lo, float hi) {
  uint32_t r;
  asm("cvt.rn.bf16x2.f32 %0, %1, %2;" : "=r"(r) : "f"(hi), "f"(lo));
  return r;
}
__device__ __forceinline__ float silu_mul(float g, float u, float hf) {
  float a = hf * g, t;
  asm("tanh.approx.f32 %0, %1;" : "=f"(t) : "f"(a));
  float p = a * u;
  return fmaf(p, t, p);
}
template <int R>
__device__ __forceinline__ void silu_step(uint32_t (&h)[4], const float (&d)[R], int j, float hf) {
#pragma unroll
  for (int i = 0; i < 4; i++)
    h[i] = pack_bf16(silu_mul(d[8 * j + 2 * i], d[R / 2 + 8 * j + 2 * i], hf), silu_mul(d[8 * j + 2 * i + 1], d[R / 2 + 8 * j + 2 * i + 1], hf));
}

template <int AOFF, int BOFF, int BHI, int SD>
__device__ __forceinline__ void wgmma_ss_n128(float (&d)[64], uint32_t alo, uint32_t blo) {
  asm volatile("{\n.reg .pred p;\n.reg .b32 al, bl;\n.reg .b64 da, db;\nsetp.ne.b32 p, %69, 0;\n"
    "add.u32 al, %64, %66;\nadd.u32 bl, %65, %67;\nmov.b64 da, {al, 0x40000040};\nmov.b64 db, {bl, %68};\n"
    "wgmma.mma_async.sync.aligned.m64n128k16.f32.bf16.bf16 {"
    "%0, %1, %2, %3, %4, %5, %6, %7, %8, %9, %10, %11, %12, %13, %14, %15, %16, %17, %18, %19, %20, %21, %22, %23, %24, %25, %26, %27, %28, %29, "
    "%30, %31, %32, %33, %34, %35, %36, %37, %38, %39, %40, %41, %42, %43, %44, %45, %46, %47, %48, %49, %50, %51, %52, %53, %54, %55, %56, %57, "
    "%58, %59, %60, %61, %62, %63}, da, db, p, 1, 1, 0, 1;\n}\n"
    : "+f"(d[0]), "+f"(d[1]), "+f"(d[2]), "+f"(d[3]), "+f"(d[4]), "+f"(d[5]), "+f"(d[6]), "+f"(d[7]), "+f"(d[8]), "+f"(d[9]), "+f"(d[10]), "+f"(d[11]),
      "+f"(d[12]), "+f"(d[13]), "+f"(d[14]), "+f"(d[15]), "+f"(d[16]), "+f"(d[17]), "+f"(d[18]), "+f"(d[19]), "+f"(d[20]), "+f"(d[21]), "+f"(d[22]),
      "+f"(d[23]), "+f"(d[24]), "+f"(d[25]), "+f"(d[26]), "+f"(d[27]), "+f"(d[28]), "+f"(d[29]), "+f"(d[30]), "+f"(d[31]), "+f"(d[32]), "+f"(d[33]),
      "+f"(d[34]), "+f"(d[35]), "+f"(d[36]), "+f"(d[37]), "+f"(d[38]), "+f"(d[39]), "+f"(d[40]), "+f"(d[41]), "+f"(d[42]), "+f"(d[43]), "+f"(d[44]),
      "+f"(d[45]), "+f"(d[46]), "+f"(d[47]), "+f"(d[48]), "+f"(d[49]), "+f"(d[50]), "+f"(d[51]), "+f"(d[52]), "+f"(d[53]), "+f"(d[54]), "+f"(d[55]),
      "+f"(d[56]), "+f"(d[57]), "+f"(d[58]), "+f"(d[59]), "+f"(d[60]), "+f"(d[61]), "+f"(d[62]), "+f"(d[63])
    : "r"(alo), "r"(blo), "n"(AOFF), "n"(BOFF), "n"(BHI), "n"(SD));
}
template <int AOFF, int BOFF, int BHI, int SD>
__device__ __forceinline__ void wgmma_ss_n64(float (&d)[32], uint32_t alo, uint32_t blo) {
  asm volatile("{\n.reg .pred p;\n.reg .b32 al, bl;\n.reg .b64 da, db;\nsetp.ne.b32 p, %37, 0;\n"
    "add.u32 al, %32, %34;\nadd.u32 bl, %33, %35;\nmov.b64 da, {al, 0x40000040};\nmov.b64 db, {bl, %36};\n"
    "wgmma.mma_async.sync.aligned.m64n64k16.f32.bf16.bf16 {"
    "%0, %1, %2, %3, %4, %5, %6, %7, %8, %9, %10, %11, %12, %13, %14, %15, %16, %17, %18, %19, %20, %21, %22, %23, %24, %25, %26, %27, %28, %29, "
    "%30, %31}, da, db, p, 1, 1, 0, 1;\n}\n"
    : "+f"(d[0]), "+f"(d[1]), "+f"(d[2]), "+f"(d[3]), "+f"(d[4]), "+f"(d[5]), "+f"(d[6]), "+f"(d[7]), "+f"(d[8]), "+f"(d[9]), "+f"(d[10]), "+f"(d[11]),
      "+f"(d[12]), "+f"(d[13]), "+f"(d[14]), "+f"(d[15]), "+f"(d[16]), "+f"(d[17]), "+f"(d[18]), "+f"(d[19]), "+f"(d[20]), "+f"(d[21]), "+f"(d[22]),
      "+f"(d[23]), "+f"(d[24]), "+f"(d[25]), "+f"(d[26]), "+f"(d[27]), "+f"(d[28]), "+f"(d[29]), "+f"(d[30]), "+f"(d[31])
    : "r"(alo), "r"(blo), "n"(AOFF), "n"(BOFF), "n"(BHI), "n"(SD));
}
template <int BOFF, int SD>
__device__ __forceinline__ void wgmma_rs(float (&d)[32], const uint32_t (&a)[4], uint32_t blo) {
  asm volatile("{\n.reg .pred p;\n.reg .b32 bl;\n.reg .b64 db;\nsetp.ne.b32 p, %38, 0;\n"
    "add.u32 bl, %36, %37;\nmov.b64 db, {bl, 0x40000040};\n"
    "wgmma.mma_async.sync.aligned.m64n64k16.f32.bf16.bf16 {"
    "%0, %1, %2, %3, %4, %5, %6, %7, %8, %9, %10, %11, %12, %13, %14, %15, %16, %17, %18, %19, %20, %21, %22, %23, %24, %25, %26, %27, %28, %29, "
    "%30, %31}, {%32, %33, %34, %35}, db, p, 1, 1, 1;\n}\n"
    : "+f"(d[0]), "+f"(d[1]), "+f"(d[2]), "+f"(d[3]), "+f"(d[4]), "+f"(d[5]), "+f"(d[6]), "+f"(d[7]), "+f"(d[8]), "+f"(d[9]), "+f"(d[10]), "+f"(d[11]),
      "+f"(d[12]), "+f"(d[13]), "+f"(d[14]), "+f"(d[15]), "+f"(d[16]), "+f"(d[17]), "+f"(d[18]), "+f"(d[19]), "+f"(d[20]), "+f"(d[21]), "+f"(d[22]),
      "+f"(d[23]), "+f"(d[24]), "+f"(d[25]), "+f"(d[26]), "+f"(d[27]), "+f"(d[28]), "+f"(d[29]), "+f"(d[30]), "+f"(d[31])
    : "r"(a[0]), "r"(a[1]), "r"(a[2]), "r"(a[3]), "r"(blo), "n"(BOFF), "n"(SD));
}
template <int BOFF, int SD>
__device__ __forceinline__ void wgmma_rs(float (&d)[16], const uint32_t (&a)[4], uint32_t blo) {
  asm volatile("{\n.reg .pred p;\n.reg .b32 bl;\n.reg .b64 db;\nsetp.ne.b32 p, %22, 0;\n"
    "add.u32 bl, %20, %21;\nmov.b64 db, {bl, 0x40000040};\n"
    "wgmma.mma_async.sync.aligned.m64n32k16.f32.bf16.bf16 {"
    "%0, %1, %2, %3, %4, %5, %6, %7, %8, %9, %10, %11, %12, %13, %14, %15}, {%16, %17, %18, %19}, db, p, 1, 1, 1;\n}\n"
    : "+f"(d[0]), "+f"(d[1]), "+f"(d[2]), "+f"(d[3]), "+f"(d[4]), "+f"(d[5]), "+f"(d[6]), "+f"(d[7]), "+f"(d[8]), "+f"(d[9]), "+f"(d[10]), "+f"(d[11]),
      "+f"(d[12]), "+f"(d[13]), "+f"(d[14]), "+f"(d[15])
    : "r"(a[0]), "r"(a[1]), "r"(a[2]), "r"(a[3]), "r"(blo), "n"(BOFF), "n"(SD));
}

__device__ __forceinline__ void untag(uint32_t& w) { asm volatile("and.b32 %0, %0, -2;" : "+r"(w)); }
__device__ __forceinline__ void h_send(uint32_t (&h)[4], char* dst, uint32_t par) {
  h[0] = (h[0] & ~1u) | par;
  asm volatile("{\n.reg .b128 t;\n.reg .b64 lo, hi;\nmov.b64 lo, {%1,%2};\nmov.b64 hi, {%3,%4};\nmov.b128 t, {lo, hi};\nst.relaxed.gpu.global.b128 [%0], t;\n}"
               ::"l"(dst), "r"(h[0]), "r"(h[1]), "r"(h[2]), "r"(h[3]) : "memory");
}
template <int J0, int J1>
__device__ __forceinline__ void h_load(uint32_t (&h)[14][4], const char* src) {
#pragma unroll
  for (int j = J0; j < J1; j++)
    asm volatile("{\n.reg .b128 t;\n.reg .b64 lo, hi;\nld.relaxed.gpu.global.b128 t, [%4];\nmov.b128 {lo, hi}, t;\nmov.b64 {%0,%1}, lo;\nmov.b64 {%2,%3}, hi;\n}"
                 : "=r"(h[j][0]), "=r"(h[j][1]), "=r"(h[j][2]), "=r"(h[j][3]) : "l"(src + j * 512) : "memory");
}
template <int J0>
__device__ __forceinline__ void h_check4(uint32_t (&h)[14][4], const char* src, uint32_t par, uint32_t zero) {
  asm volatile("{\n.reg .pred p;\n.reg .b32 b, t, n;\n.reg .b128 v;\n.reg .b64 lo, hi;\nmov.u32 n, 0;\n"
               "AGAIN:\nmov.b32 b, %18;\nxor.b32 t, %0, %17;\nor.b32 b, b, t;\nxor.b32 t, %4, %17;\nor.b32 b, b, t;\nxor.b32 t, %8, %17;\nor.b32 b, b, t;\nxor.b32 t, %12, %17;\nor.b32 b, b, t;\n"
               "and.b32 b, b, 1;\nsetp.ne.u32 p, b, 0;\nvote.sync.any.pred p, p, 0xffffffff;\n@!p bra OK;\n"
               "add.u32 n, n, 1;\nsetp.gt.u32 p, n, 0x40000;\n@p exit;\n"
               "ld.relaxed.gpu.global.b128 v, [%16 + 0];\nmov.b128 {lo, hi}, v;\nmov.b64 {%0,%1}, lo;\nmov.b64 {%2,%3}, hi;\n"
               "ld.relaxed.gpu.global.b128 v, [%16 + 512];\nmov.b128 {lo, hi}, v;\nmov.b64 {%4,%5}, lo;\nmov.b64 {%6,%7}, hi;\n"
               "ld.relaxed.gpu.global.b128 v, [%16 + 1024];\nmov.b128 {lo, hi}, v;\nmov.b64 {%8,%9}, lo;\nmov.b64 {%10,%11}, hi;\n"
               "ld.relaxed.gpu.global.b128 v, [%16 + 1536];\nmov.b128 {lo, hi}, v;\nmov.b64 {%12,%13}, lo;\nmov.b64 {%14,%15}, hi;\n"
               "bra AGAIN;\nOK:\nand.b32 %0, %0, -2;\nand.b32 %4, %4, -2;\nand.b32 %8, %8, -2;\nand.b32 %12, %12, -2;\n}"
               : "+r"(h[J0+0][0]), "+r"(h[J0+0][1]), "+r"(h[J0+0][2]), "+r"(h[J0+0][3]), "+r"(h[J0+1][0]), "+r"(h[J0+1][1]), "+r"(h[J0+1][2]), "+r"(h[J0+1][3]),
                 "+r"(h[J0+2][0]), "+r"(h[J0+2][1]), "+r"(h[J0+2][2]), "+r"(h[J0+2][3]), "+r"(h[J0+3][0]), "+r"(h[J0+3][1]), "+r"(h[J0+3][2]), "+r"(h[J0+3][3])
               : "l"(src + J0 * 512), "r"(par), "r"(zero) : "memory");
}
template <int J0>
__device__ __forceinline__ void h_check2(uint32_t (&h)[14][4], const char* src, uint32_t par, uint32_t zero) {
  asm volatile("{\n.reg .pred p;\n.reg .b32 b, t, n;\n.reg .b128 v;\n.reg .b64 lo, hi;\nmov.u32 n, 0;\n"
               "AGAIN:\nmov.b32 b, %10;\nxor.b32 t, %0, %9;\nor.b32 b, b, t;\nxor.b32 t, %4, %9;\nor.b32 b, b, t;\n"
               "and.b32 b, b, 1;\nsetp.ne.u32 p, b, 0;\nvote.sync.any.pred p, p, 0xffffffff;\n@!p bra OK;\n"
               "add.u32 n, n, 1;\nsetp.gt.u32 p, n, 0x40000;\n@p exit;\n"
               "ld.relaxed.gpu.global.b128 v, [%8 + 0];\nmov.b128 {lo, hi}, v;\nmov.b64 {%0,%1}, lo;\nmov.b64 {%2,%3}, hi;\n"
               "ld.relaxed.gpu.global.b128 v, [%8 + 512];\nmov.b128 {lo, hi}, v;\nmov.b64 {%4,%5}, lo;\nmov.b64 {%6,%7}, hi;\n"
               "bra AGAIN;\nOK:\nand.b32 %0, %0, -2;\nand.b32 %4, %4, -2;\n}"
               : "+r"(h[J0+0][0]), "+r"(h[J0+0][1]), "+r"(h[J0+0][2]), "+r"(h[J0+0][3]), "+r"(h[J0+1][0]), "+r"(h[J0+1][1]), "+r"(h[J0+1][2]), "+r"(h[J0+1][3])
               : "l"(src + J0 * 512), "r"(par), "r"(zero) : "memory");
}

template <int K, int R>
__device__ __forceinline__ void out_stage(const float (&d)[R], uint32_t tile, int lane) {
  constexpr int CH = R / 4;
  const int sr = lane & 15, c = 2 * K + (lane >> 4);
  asm volatile("stmatrix.sync.aligned.m8n8.x4.shared.b16 [%0], {%1, %2, %3, %4};"
               ::"r"(tile + sr * (CH * 16) + ((c ^ ((R == 16 ? sr >> 1 : sr) & (CH - 1))) << 4)),
                 "r"(pack_bf16(d[8 * K], d[8 * K + 1])), "r"(pack_bf16(d[8 * K + 2], d[8 * K + 3])),
                 "r"(pack_bf16(d[8 * K + 4], d[8 * K + 5])), "r"(pack_bf16(d[8 * K + 6], d[8 * K + 7])) : "memory");
}
template <int BLK, int J0, int J1, bool ZERO = false, int COFF = 0, int R>
__device__ __forceinline__ void p2(float (&acc)[R], const uint32_t (&h)[14][4], uint32_t d0, uint32_t om, uint32_t op) {
  wg_fence();
  static_for<J0, J1>([&](auto jc) {
    constexpr int j = decltype(jc)::value;
    wgmma_rs<(int)(w2_blk(BLK) >> 4) + COFF + (j < 12 ? j : j - 12) * 128, (ZERO && j == J0) ? 0 : 1>(acc, h[j], d0 + (j < 12 ? om : op));
  });
}

struct ClusterMap { uint8_t v[64]; };

__global__ void __cluster_dims__(2, 1, 1) __launch_bounds__(384, 1)
swiglu_fused_kernel(const __nv_bfloat16* __restrict__ x, const __nv_bfloat16* __restrict__ w1, const __nv_bfloat16* __restrict__ w3,
                    __nv_bfloat16* __restrict__ out, const __grid_constant__ ClusterMap cmap,
                    const __grid_constant__ CUtensorMap tm_x, const __grid_constant__ CUtensorMap tm_w1,
                    const __grid_constant__ CUtensorMap tm_w3, const __grid_constant__ CUtensorMap tm_w1s,
                    const __grid_constant__ CUtensorMap tm_w3s, const __grid_constant__ CUtensorMap tm_w2,
                    const __grid_constant__ CUtensorMap tm_o64, const __grid_constant__ CUtensorMap tm_o32) {
  extern __shared__ __align__(1024) uint8_t smem_raw[];
  const uint32_t sb = smem_u32(smem_raw);
  const uint32_t bars = sb + BAR_OFF;
  const int tid = threadIdx.x, lane = tid & 31;
  const uint32_t rank = blockIdx.x & 1;
  const uint32_t bid = rank | cmap.v[blockIdx.x >> 1];
  const int f = (bid >> 1) & 7, m = ((bid >> 4) << 1) | (int)rank;
  const int odd = f & 1, q = f >> 1;
  const int a0 = 224 * f + 32 * odd;

  if (tid < 256) {
    const uint32_t ln = tid >> 3, c16 = (tid & 7) << 4, sw = c16 ^ ((ln & 7) << 4);
    const char* xs = (const char*)x + (m * 128 + ln) * (kD * 2) + c16;
    const uint32_t wo = ln * (kF * 2) + a0 * 2 + c16;
    const uint32_t xd = sb + X_OFF + ln * 128 + sw, wd = sb + R_OFF + ln * 128 + sw;
#pragma unroll
    for (int i = 0; i < 4; i++) cp_async16(xd + i * 4096, xs + i * 32 * (kD * 2));
    cp_async16(wd, (const char*)w1 + wo);
    cp_async16(wd + 8192, (const char*)w3 + wo);
    asm volatile("cp.async.commit_group;" ::: "memory");
    cp_async16(wd + 4096, (const char*)w1 + wo + 32 * (kF * 2));
    cp_async16(wd + 8192 + 4096, (const char*)w3 + wo + 32 * (kF * 2));
    asm volatile("cp.async.commit_group;" ::: "memory");
  }
  const int warp = __shfl_sync(0xffffffffu, tid >> 5, 0);
  const CUtensorMap* tw = rank ? &tm_w3 : &tm_w1;
  auto load_unit = [&](int n) {
    tma_load_mc(sb + R_OFF + (n % 7) * 16384 + rank * 8192, tw, bars + 8 * b_fu(n), a0 + 64 * u_grp(n), 64 * u_kb(n));
    if (u_newx(n + 1)) tma_load(sb + X_OFF + u_kb(n + 1) * 16384, &tm_x, bars + 8 * b_fx(u_kb(n + 1)), 64 * u_kb(n + 1), m * 128);
  };
  if (warp == 8) {
    if (lane == 0) {
      tma_prefetch_desc(tw); tma_prefetch_desc(&tm_x);
      static_for<3, 13>([&](auto i) { mbar_init(bars + 8 * decltype(i)::value, 1); });
    }
    __syncwarp();
    if (lane < 10) mbar_expect(bars + 8 * (3 + lane), 16384);
    asm volatile("fence.mbarrier_init.release.cluster;" ::: "memory");
    cluster_arrive(); cluster_wait(); cluster_arrive();
    if (lane == 0) {
#pragma unroll
      for (int n = 1; n < 7; n++) load_unit(n);
    }
    __syncwarp();
    cluster_wait();
  } else if (warp > 8) {
    cluster_arrive();
  } else {
    cluster_arrive();
    cluster_wait(); cluster_arrive();
  }
  int role;
  asm volatile("shfl.sync.idx.b32 %0, %1, 0, 0x1f, 0xffffffff;" : "=r"(role) : "r"(tid >> 8) : "memory");
  if (role) {
    asm volatile("setmaxnreg.dec.sync.aligned.u32 40;");
    if (warp > 8) {
      if (warp == 9) {
        if (lane == 0) static_for<13, 29>([&](auto i) { mbar_init(bars + 8 * decltype(i)::value, 1); });
        __syncwarp();
        if (lane < 16) mbar_expect(bars + 8 * (13 + lane), 16384);
      } else if (warp == 10) {
        if (lane == 0) static_for<30, 43>([&](auto i) { mbar_init(bars + 8 * decltype(i)::value, 1); });
        __syncwarp();
        if (lane < 9) mbar_expect(bars + 8 * (30 + lane), lane == 0 ? 32768 : lane == 1 ? 24576 : 28672);
      } else {
        if (lane == 0) static_for<45, B_NUM>([&](auto i) { mbar_init(bars + 8 * decltype(i)::value, decltype(i)::value < b_st(0) ? 16 : 4); });
      }
      asm volatile("fence.mbarrier_init.release.cluster;" ::: "memory");
      cluster_wait(); cluster_arrive(); cluster_wait();
    }
    if (warp == 8) {
      if (lane == 0) {
        const CUtensorMap* tws = rank ? &tm_w3s : &tm_w1s;
        tma_prefetch_desc(tws); tma_prefetch_desc(&tm_w2);
#pragma unroll
        for (int n = 7; n < 21; n++) { mbar_wait(bars + 8 * b_cu(n - 7)); load_unit(n); }
#pragma unroll
        for (int u = 0; u < 7; u++) {
          if ((u & 1) == 0) mbar_wait(bars + 8 * b_cu(14 + u / 2));
          tma_load_mc(sb + R_OFF + u * 8192 + rank * 4096, tws, bars + 8 * b_fs(u), 224 * f + (odd ? 0 : 192), 64 * u);
        }
        const int row_own = 224 * f + 112 * rank, row_peer = 224 * (f ^ 1) + 112 * rank;
#pragma unroll
        for (int i = 0; i < 7; i++) {
          if (i < 2) mbar_wait(bars + 8 * b_cu(19 + i));
          else if (i < 5) mbar_wait(bars + 8 * b_cs(i == 2 ? 1 : i == 3 ? 3 : 6));
          else if (i == 6) mbar_wait(bars + 8 * B_PACE);
          tma_load_mc(sb + w2_blk(i) + rank * 14336, &tm_w2, bars + 8 * b_fw(i), i ? 256 * odd + 64 * ((q + (i - 1) / 2) % 3) : 192,
                      (i & 1) || i == 0 ? row_own : row_peer);
        }
      }
    } else if (warp < 11) {
      const int g = warp - 9;
      if (lane == 0) { tma_prefetch_desc(&tm_o64); tma_prefetch_desc(&tm_o32); }
      mbar_wait(bars + 8 * b_fu(17));
      mbar_wait(bars + 8 * B_TAG);
      if (lane < 8) {
        uint32_t e, v, n = 0;
        asm volatile("ld.shared.u32 %0, [%1];" : "=r"(e) : "r"(sb + TAG_OFF + 4) : "memory");
        do { asm volatile("ld.acquire.gpu.global.u32 %0, [%1];" : "=r"(v) : "l"(g_zflag + ((bid & ~14u) | (lane << 1))) : "memory"); } while (v != e && ++n < 0x40000);
      }
      __syncwarp();
      if (lane == 0) {
        asm volatile("fence.proxy.async;" ::: "memory");
#pragma unroll
        for (int i = 0; i < 5; i++) {
          mbar_wait(bars + 8 * (b_st(i) + 5 * g));
          asm volatile("fence.proxy.async.shared::cta;" ::: "memory");
          asm volatile("cp.reduce.async.bulk.tensor.2d.global.shared::cta.add.tile.bulk_group [%0, {%2, %3}], [%1];"
                       ::"l"(i < 3 ? &tm_o64 : &tm_o32), "r"(sb + stg_off(i) + g * (i < 3 ? 8192 : 4096)),
                         "r"(i ? 256 * odd + 64 * ((q + (i < 3 ? i - 1 : 2)) % 3) + (i == 4 ? 32 : 0) : 192), "r"(m * 128 + g * 64) : "memory");
        }
        asm volatile("cp.async.bulk.commit_group;\ncp.async.bulk.wait_group.read 0;" ::: "memory");
      }
    } else {
      const uint32_t e = g_epoch[bid] + 1;
      __syncwarp();
      if (lane == 0) {
        g_epoch[bid] = e;
        asm volatile("st.shared.v2.u32 [%0], {%1, %2};" ::"r"(sb + TAG_OFF), "r"(e & 1u), "r"(e) : "memory");
        mbar_arrive(bars + 8 * B_TAG);
      }
      mbar_wait(bars + 8 * b_fu(8));
      char* z = (char*)(out + (size_t)(m * 128 + q * 32) * kD + 224 * odd) + lane * 16;
      if (lane < 28) {
#pragma unroll 4
        for (int r = 0; r < 32; r++) asm volatile("st.global.v4.b32 [%0], {%1, %1, %1, %1};" ::"l"(z + r * (kD * 2)), "r"(0) : "memory");
      }
      __syncwarp();
      if (lane == 0) {
        asm volatile("fence.acq_rel.gpu;" ::: "memory");
        asm volatile("st.relaxed.gpu.global.u32 [%0], %1;" ::"l"(g_zflag + bid), "r"(e) : "memory");
      }
    }
  } else {
    const int g = warp >> 2;
    uint32_t cbars;
    asm volatile("mapa.shared::cluster.u32 %0, %1, %2;" : "=r"(cbars) : "r"(bars), "r"(lane & 1));
    auto SF = [&]() { sched_fence(bars + 8 * B_TAG); };
    auto release = [&](int b) { if (lane < 2) mbar_arrive_cluster(cbars + 8 * b); };
    auto wait_w2 = [&](int i) { mbar_wait(bars + 8 * b_fw(i)); };
    auto passed = [&](int k) { if (lane == 0) mbar_arrive(bars + 8 * (b_wg(k) + g)); };
    auto other_passed = [&](int k) { mbar_wait(bars + 8 * (b_wg(k) + 1 - g)); };
    auto tile = [&](int i) { return sb + stg_off(i) + warp * (i < 3 ? 2048 : 1024); };
    auto staged = [&](int i) { __syncwarp(); if (lane == 0) mbar_arrive(bars + 8 * (b_st(i) + 5 * g)); };

    const uint32_t dx = desc_lo(sb + X_OFF + g * 8192, 16);
    const uint32_t du = desc_lo(sb + R_OFF, 8192), ds = desc_lo(sb + R_OFF, 4096), dw = desc_lo(sb, 16);
    const uint32_t om = odd ? 256u : 0u, op = odd ? 0u : 1536u;
#define OWN ho, dw, om, op
#define PEER hp, dw, 256u - om, 1536u - op
    char* hx_own = (char*)g_hx + (size_t)bid * 57344 + warp * 7168 + lane * 16;
    const char* hx_peer = (const char*)g_hx + (size_t)(bid ^ 2) * 57344 + warp * 7168 + lane * 16;

    uint32_t ho[14][4], hp[14][4];
    uint32_t par;
    float accP[32], accQ[32], accS[32];
    {
      float acc0[64], acc1[64], acc2[64];
      static_for<0, 21>([&](auto nc) {
        constexpr int n = decltype(nc)::value, kb = u_kb(n), bo = (n % 7) * 1024;
        if constexpr (n == 0) {
          asm volatile("cp.async.wait_group 1;\nfence.proxy.async.shared::cta;\nbar.sync 1, 256;" ::: "memory");
        } else {
          if (u_newx(n)) mbar_wait(bars + 8 * b_fx(kb));
          mbar_wait(bars + 8 * b_fu(n));
        }
        auto mma = [&](auto& acc) {
          wg_fence();
          wgmma_ss_n128<kb * 1024, bo, DHI_128, kb ? 1 : 0>(acc, dx, du);
          wgmma_ss_n128<kb * 1024 + 2, bo + 128, DHI_128, 1>(acc, dx, du);
          if constexpr (n == 0) {
            asm volatile("cp.async.wait_group 0;\nfence.proxy.async.shared::cta;\nbar.sync 1, 256;" ::: "memory");
            wg_fence();
          }
          wgmma_ss_n128<kb * 1024 + 4, bo + 256, DHI_128, 1>(acc, dx, du);
          wgmma_ss_n128<kb * 1024 + 6, bo + 384, DHI_128, 1>(acc, dx, du);
          wg_commit();
        };
        if constexpr (u_grp(n) == 0) mma(acc0); else if constexpr (u_grp(n) == 1) mma(acc1); else mma(acc2);
        if constexpr (n == 1) cluster_wait();
        if constexpr (n == 5) {
          asm volatile("setmaxnreg.inc.sync.aligned.u32 232;");
          mbar_wait(bars + 8 * B_TAG);
          asm volatile("ld.shared.u32 %0, [%1];" : "=r"(par) : "r"(sb + TAG_OFF) : "memory");
        }
        auto rel = [&]() { wg_wait<1>(); if constexpr (n != 19) release(b_cu(n - 1)); };
        constexpr bool early = n <= 10 || n == 14;
        if constexpr (n > 0 && early) rel();
        if constexpr (n >= 10) {
          SF();
          if constexpr (n >= 14) h_load<n - 14, n - 13>(hp, hx_peer);
          if constexpr (n < 18) {
            if constexpr (n < 14) silu_step(ho[n - 10], acc0, n - 10, half_now()); else silu_step(ho[n - 10], acc1, n - 14, half_now());
            h_send(ho[n - 10], hx_own + (n - 10) * 512, par);
          }
          if constexpr (!early) { SF(); rel(); }
        }
      });
      static_for<0, 7>([&](auto uc) {
        constexpr int u = decltype(uc)::value;
        if (u == 0 || u == 4) mbar_wait(bars + 8 * b_fs(u));
        wg_fence();
        wgmma_ss_n64<u * 1024, u * 512, DHI_64, u ? 1 : 0>(accS, dx, ds);
        wgmma_ss_n64<u * 1024 + 2, u * 512 + 64, DHI_64, 1>(accS, dx, ds);
        wgmma_ss_n64<u * 1024 + 4, u * 512 + 128, DHI_64, 1>(accS, dx, ds);
        wgmma_ss_n64<u * 1024 + 6, u * 512 + 192, DHI_64, 1>(accS, dx, ds);
        wg_commit();
        if constexpr (u == 0) {
          SF();
          h_load<7, 8>(hp, hx_peer);
          static_for<0, 8>([&](auto j) { untag(ho[decltype(j)::value][0]); });
        }
        if constexpr (u == 1) { wg_wait<2>(); release(b_cu(20)); }
        if constexpr (u == 1 || u == 4) {
          constexpr int j = u == 1 ? 0 : 2;
          SF();
          const float hf = half_now();
          silu_step(ho[8 + j], acc2, j, hf); h_send(ho[8 + j], hx_own + (8 + j) * 512, par);
          silu_step(ho[9 + j], acc2, j + 1, hf); h_send(ho[9 + j], hx_own + (9 + j) * 512, par);
          SF();
        }
        if constexpr (u == 3 || u == 5) { wg_wait<2>(); release(b_cs(u - 2)); }
      });
    }
    wait_w2(0);
    p2<0, 0, 6, true>(accQ, OWN);
    wg_commit();
    wg_wait<1>();
    release(b_cs(6));
    passed(0);
    p2<0, 6, 8>(accQ, OWN);
    SF();
    silu_step(ho[12], accS, 0, half_now()); h_send(ho[12], hx_own + 12 * 512, par);
    SF();
    untag(ho[8][0]); untag(ho[9][0]); untag(ho[10][0]); untag(ho[11][0]);
    p2<0, 8, 12>(accQ, OWN);
    SF();
    silu_step(ho[13], accS, 1, half_now()); h_send(ho[13], hx_own + 13 * 512, par);
    wait_w2(1);
    p2<1, 0, 4, true>(accP, OWN);
    untag(ho[12][0]); untag(ho[13][0]);
    p2<0, 12, 14>(accQ, OWN);
    wg_commit();
    p2<1, 4, 10>(accP, OWN);
    wg_commit();
    SF();
    h_check4<0>(hp, hx_peer, par, zero_now()); h_check4<4>(hp, hx_peer, par, zero_now());
    other_passed(0);
    wg_wait<1>();
    acc_ready(accQ);
    passed(1);
    SF();
    out_stage<0>(accQ, tile(0), lane); out_stage<1>(accQ, tile(0), lane);
    SF();
    p2<1, 10, 14>(accP, OWN);
    SF();
    out_stage<2>(accQ, tile(0), lane); out_stage<3>(accQ, tile(0), lane);
    staged(0);
    h_load<8, 14>(hp, hx_peer);
    if (tid == 0) mbar_arrive(bars + 8 * B_PACE);
    wait_w2(2);
    p2<2, 0, 8>(accP, PEER);
    wait_w2(3);
    p2<3, 0, 4, true>(accQ, OWN);
    SF();
    h_check2<8>(hp, hx_peer, par, zero_now()); h_check4<10>(hp, hx_peer, par, zero_now());
    p2<2, 8, 14>(accP, PEER);
    wg_commit();
    p2<3, 4, 10>(accQ, OWN);
    wg_commit();
    other_passed(1);
    wg_wait<1>();
    acc_ready(accP);
    passed(2);
    SF();
    out_stage<0>(accP, tile(1), lane); out_stage<1>(accP, tile(1), lane);
    SF();
    p2<3, 10, 14>(accQ, OWN);
    SF();
    out_stage<2>(accP, tile(1), lane); out_stage<3>(accP, tile(1), lane);
    staged(1);
    wait_w2(4);
    p2<4, 0, 14>(accQ, PEER);
    wg_commit();
    float accA[16], accB[16];
    wait_w2(5);
    p2<5, 0, 8, true, 0>(accA, OWN);
    wg_commit();
    other_passed(2);
    wg_wait<1>();
    acc_ready(accQ);
    SF();
    out_stage<0>(accQ, tile(2), lane); out_stage<1>(accQ, tile(2), lane);
    SF();
    p2<5, 8, 14, false, 0>(accA, OWN);
    SF();
    out_stage<2>(accQ, tile(2), lane); out_stage<3>(accQ, tile(2), lane);
    staged(2);
    wait_w2(6);
    p2<6, 0, 14, false, 0>(accA, PEER);
    wg_commit();
    p2<5, 0, 8, true, 4>(accB, OWN);
    wg_commit();
    wg_wait<1>();
    acc_ready(accA);
    out_stage<0>(accA, tile(3), lane); out_stage<1>(accA, tile(3), lane);
    staged(3);
    SF();
    p2<5, 8, 14, false, 4>(accB, OWN);
    p2<6, 0, 14, false, 4>(accB, PEER);
    wg_commit();
    wg_wait<0>();
    acc_ready(accB);
    out_stage<0>(accB, tile(4), lane); out_stage<1>(accB, tile(4), lane);
    staged(4);
#undef OWN
#undef PEER
  }
}

__global__ void occupancy_probe_kernel() {}

typedef CUresult (*EncodeFn)(CUtensorMap*, CUtensorMapDataType, cuuint32_t, void*, const cuuint64_t*, const cuuint64_t*,
                             const cuuint32_t*, const cuuint32_t*, CUtensorMapInterleave, CUtensorMapSwizzle,
                             CUtensorMapL2promotion, CUtensorMapFloatOOBfill);

void make_map(EncodeFn fn, CUtensorMap* tm, const void* p, uint64_t cols, uint64_t rows, uint32_t bc, uint32_t br) {
  cuuint64_t dims[2] = {cols, rows};
  cuuint64_t strides[1] = {cols * 2};
  cuuint32_t box[2] = {bc, br};
  cuuint32_t es[2] = {1, 1};
  fn(tm, CU_TENSOR_MAP_DATA_TYPE_BFLOAT16, 2, const_cast<void*>(p), dims, strides, box, es, CU_TENSOR_MAP_INTERLEAVE_NONE,
     bc == 64 ? CU_TENSOR_MAP_SWIZZLE_128B : CU_TENSOR_MAP_SWIZZLE_64B, CU_TENSOR_MAP_L2_PROMOTION_L2_128B,
     CU_TENSOR_MAP_FLOAT_OOB_FILL_NONE);
}

}

extern "C" void kernel_launch(void* const* d_in, const int* in_sizes, int n_in, void* d_out, int out_size) {
  (void)in_sizes; (void)n_in; (void)out_size;
  static EncodeFn fn = nullptr;
  static int clusters_of_8 = 0;
  if (!fn) {
    void* p = nullptr;
    cudaDriverEntryPointQueryResult qr;
    cudaGetDriverEntryPoint("cuTensorMapEncodeTiled", &p, cudaEnableDefault, &qr);
    fn = (EncodeFn)p;
    cudaFuncSetAttribute(swiglu_fused_kernel, cudaFuncAttributeMaxDynamicSharedMemorySize, SMEM_BYTES);
    cudaFuncSetAttribute(occupancy_probe_kernel, cudaFuncAttributeMaxDynamicSharedMemorySize, SMEM_BYTES);
    cudaLaunchConfig_t cfg = {};
    cudaLaunchAttribute at;
    at.id = cudaLaunchAttributeClusterDimension;
    at.val.clusterDim.x = 8; at.val.clusterDim.y = 1; at.val.clusterDim.z = 1;
    cfg.gridDim = dim3(kNumCtas); cfg.blockDim = dim3(384); cfg.dynamicSmemBytes = SMEM_BYTES; cfg.attrs = &at; cfg.numAttrs = 1;
    if (cudaOccupancyMaxActiveClusters(&clusters_of_8, occupancy_probe_kernel, &cfg) != cudaSuccess) { clusters_of_8 = 0; (void)cudaGetLastError(); }
  }
  CUtensorMap tx, tw1, tw3, tw1s, tw3s, tw2, to64, to32;
  make_map(fn, &tx, d_in[0], kD, kM, 64, 128);
  make_map(fn, &tw1, d_in[1], kF, kD, 64, 64);
  make_map(fn, &tw3, d_in[2], kF, kD, 64, 64);
  make_map(fn, &tw1s, d_in[1], kF, kD, 32, 64);
  make_map(fn, &tw3s, d_in[2], kF, kD, 32, 64);
  make_map(fn, &tw2, d_in[3], kD, kF, 64, 112);
  make_map(fn, &to64, d_out, kD, kM, 64, 64);
  make_map(fn, &to32, d_out, kD, kM, 32, 64);
  ClusterMap cm;
  for (int c = 0; c < 64; c++)
    cm.v[c] = (uint8_t)(2 * (clusters_of_8 != 15 ? c % 8 * 8 + c / 8
                             : c < 4 ? 60 + c : c < 36 ? (c - 4) % 8 * 8 + (c - 4) / 8 : (c - 36) % 7 * 8 + 4 + (c - 36) / 7));
  swiglu_fused_kernel<<<kNumCtas, 384, SMEM_BYTES>>>((const __nv_bfloat16*)d_in[0], (const __nv_bfloat16*)d_in[1], (const __nv_bfloat16*)d_in[2],
                                                     (__nv_bfloat16*)d_out, cm, tx, tw1, tw3, tw1s, tw3s, tw2, to64, to32);
}
```
